```python
import torch

def _softmax(x, axis=-1):
    return torch.softmax(x, dim=axis)
def _gelu(x):
    return torch.nn.functional.gelu(x, approximate="tanh")
def _silu(x):
    return torch.nn.functional.silu(x)
def _sigmoid(x):
    return torch.sigmoid(x)
def _layernorm(x, axis=-1, eps=1e-5):
    m = x.mean(dim=axis, keepdim=True)
    v = x.var(dim=axis, keepdim=True, unbiased=False)
    return (x - m) / torch.sqrt(v + eps)
def _scatter_add(tgt, idx, src, axis=0):
    return tgt.clone().index_add_(axis, idx, src)
def _segment_sum(src, seg, n):
    out = torch.zeros((n,) + src.shape[1:], dtype=src.dtype)
    return out.index_add_(0, seg, src)
def _pad(x, pw):
    flat = tuple(v for pair in reversed(pw) for v in pair)
    return torch.nn.functional.pad(x, flat)

kernel_name = 'sequential_preLN__spectral_gfnet__moe_arch_mod__prompt'

def setup_inputs():

    _w = (lambda a: (lambda t: t.to(torch.bfloat16) if t.is_floating_point() else t)(torch.as_tensor(a)))
    def _A_setup():
        B, S, D = 1, 2048, 1024
        Df = D // 2 + 1
        return {
            "x": _w((lambda *s: torch.randn(*s, dtype=torch.bfloat16) * 0.05)(B, S, D)),
            "w_r": _w((lambda *s: torch.randn(*s, dtype=torch.bfloat16) * 0.4)(S, Df) * 0.02),
            "w_i": _w((lambda *s: torch.randn(*s, dtype=torch.bfloat16) * 0.4)(S, Df) * 0.02),
        }
    _A_in = _A_setup()

    def _B_setup():
        B, S, D, F, C = 1, 2048, 1024, 3584, 1
        return {
            "x": _w((lambda *s: torch.randn(*s, dtype=torch.bfloat16) * 0.05)(B, S, D)),
            "w_r": _w((lambda *s: torch.randn(*s, dtype=torch.bfloat16) * 0.2)(D)),
            "w_gate": _w((lambda *s: torch.randn(*s, dtype=torch.bfloat16) * 0.2)(D, F)),
            "w_up": _w((lambda *s: torch.randn(*s, dtype=torch.bfloat16) * 0.2)(D, F)),
            "w_down": _w((lambda *s: torch.randn(*s, dtype=torch.bfloat16) * 0.2)(F, D)),
        }
    _B_in = _B_setup()

    return {
        "A_x": _A_in["x"],
        "A_w_r": _A_in["w_r"],
        "A_w_i": _A_in["w_i"],
        "B_x": _B_in["x"],
        "B_w_r": _B_in["w_r"],
        "B_w_gate": _B_in["w_gate"],
        "B_w_up": _B_in["w_up"],
        "B_w_down": _B_in["w_down"],
    }

def reference(A_x, A_w_r, A_w_i, B_x, B_w_r, B_w_gate, B_w_up, B_w_down):
    def _A_ref(x, w_r, w_i):
        B, S, D = x.shape
        X = (lambda x, axes=(-2,-1): torch.fft.rfft2(x.float(), dim=axes))(x, axes=(-2, -1))
        W = w_r + 1j * w_i
        X = X * W
        y = (lambda x, s, axes=(-2,-1): torch.fft.irfft2(x, s=s, dim=axes).to(torch.bfloat16))(X, (S, D), axes=(-2, -1))
        return y

    def _B_ref(x, w_r, w_gate, w_up, w_down):
        B, S, D = x.shape
        C = 1
        r = x @ w_r
        idx = torch.argsort(-r, axis=-1)[:, :C]
        idx_e = (lambda x, n, axis: torch.repeat_interleave(x, n, dim=axis))(idx.reshape(B, C, 1), D, axis=2)
        x_sel = (lambda x, i, axis: torch.take_along_dim(x, i, dim=axis))(x, idx_e, axis=1)
        g = _silu(x_sel @ w_gate)
        u = x_sel @ w_up
        y = (g * u) @ w_down
        r_sel = _sigmoid((lambda x, i, axis: torch.take_along_dim(x, i, dim=axis))(r, idx, axis=1))
        y = y * r_sel.reshape(B, C, 1)
        b_off = (torch.arange(B) * S).reshape(B, 1)
        flat_idx = (idx + b_off).reshape(B * C)
        zero = (x * 0.0).reshape(B * S, D)
        upd = _scatter_add(zero, flat_idx, y.reshape(B * C, D), axis=0)
        return x + upd.reshape(B, S, D)

    x = A_x
    h = x + _A_ref(_layernorm(x, axis=-1), A_w_r, A_w_i)
    h2 = h + _B_ref(_layernorm(h, axis=-1), B_w_r, B_w_gate, B_w_up, B_w_down)
    return h2
```

```cpp
#include <cuda_runtime.h>
#include <cuda.h>
#include <cuda_bf16.h>
#include <cuda_fp16.h>
#include <stdint.h>
#include <stdio.h>

typedef uint32_t u32;
typedef unsigned long long u64;

#define STAMPX(k)
#define STAMP(k)
#define STAMP_BEGIN()
#define STAMP_END()

__device__ uint4 g_E1[262144];
__device__ uint4 g_E2[262144];
__device__ uint2 g_E1x[2048], g_E2x[2048];
__device__ u32 g_cnt[4 * 64];
__device__ u32 g_exp[160];
__device__ uint2 g_key[128];
__device__ ulonglong2 g_best;
__device__ uint4 g_candN[128 * 256], g_candH[128 * 256];
__device__ uint4 g_part[112 * 256];

#define SM_R2 0
#define SM_R0 131072
#define SM_R1 163840
#define SM_TB 215552
#define SM_MI 229888
#define MI_BAR 0
#define MI_SIDE 256
#define MI_WMAX 288
#define MI_KEYS 320
#define MI_TAG 352
#define MI_GK 356
#define MI_CROW 364
#define MI_RUN 368
#define MI_EXP 384
#define MI_RED2 640
#define SMEM_BYTES 230912
#define B_TAG 0
#define B_W 1
#define B_ST 2
#define B_LD 4
#define B_GU 6
#define B_XF 7
#define B_FREE 8
#define B_GK 10
#define B_P3 11
#define B_RING 12
#define B_T2 20
#define B_T3 21
#define B_WD 22
#define B_G 23
#define B_E2 24
#define B_NUM 25

#define PROMO CU_TENSOR_MAP_L2_PROMOTION_L2_256B
#define PDELAY 200
#define NSW1 6
#define NSW2 16
#define WAITX 1700
#define ACKW 1
#define DEPA 2
#define DEPB 3
#define DEPC 4
#define SPIN_LIMIT (1 << 22)
#define TRAP()

__device__ __forceinline__ u32 su(const void* p) { return (u32)__cvta_generic_to_shared(p); }
__device__ __forceinline__ void mb_init(u32 b, int c) { asm volatile("mbarrier.init.shared::cta.b64 [%0], %1;" ::"r"(b), "r"(c) : "memory"); }
__device__ __forceinline__ void mb_expect(u32 b, u32 n) { asm volatile("mbarrier.arrive.expect_tx.shared::cta.b64 _, [%0], %1;" ::"r"(b), "r"(n) : "memory"); }
__device__ __forceinline__ void mb_arrive(u32 b) { asm volatile("mbarrier.arrive.shared::cta.b64 _, [%0];" ::"r"(b) : "memory"); }
__device__ __forceinline__ void mb_wait(u32 b, u32 ph) {
#pragma unroll 1
    for (int i = 0; i < 32 * SPIN_LIMIT; i++) {
        u32 ok;
        asm volatile("{.reg .pred p; mbarrier.try_wait.parity.shared::cta.b64 p, [%1], %2; selp.u32 %0,1,0,p;}" : "=r"(ok) : "r"(b), "r"(ph) : "memory");
        if (ok) return;
    }
    TRAP();
}
__device__ __forceinline__ bool mb_test(u32 b, u32 ph) {
    u32 ok;
    asm volatile("{.reg .pred p; mbarrier.test_wait.parity.shared::cta.b64 p, [%1], %2; selp.u32 %0,1,0,p;}" : "=r"(ok) : "r"(b), "r"(ph) : "memory");
    return ok;
}
__device__ __forceinline__ void bulk_g2s(u32 d, const void* s, u32 n, u32 b) {
    asm volatile("cp.async.bulk.shared::cluster.global.mbarrier::complete_tx::bytes [%0], [%1], %2, [%3];" ::"r"(d), "l"(s), "r"(n), "r"(b) : "memory");
}
__device__ __forceinline__ void tma_ld(u32 d, const CUtensorMap* m, int c0, int c1, u32 b) {
    asm volatile("cp.async.bulk.tensor.2d.shared::cluster.global.mbarrier::complete_tx::bytes [%0], [%1, {%3,%4}], [%2];" ::"r"(d), "l"(m), "r"(b), "r"(c0), "r"(c1) : "memory");
}
__device__ __forceinline__ u64 pol_stream() { u64 p; asm("createpolicy.fractional.L2::evict_first.b64 %0, 1.0;" : "=l"(p)); return p; }
__device__ __forceinline__ void bulk_g2s_s(u32 d, const void* s, u32 n, u32 b) {
    asm volatile("cp.async.bulk.shared::cluster.global.mbarrier::complete_tx::bytes.L2::cache_hint [%0], [%1], %2, [%3], %4;" ::"r"(d), "l"(s), "r"(n), "r"(b), "l"(pol_stream()) : "memory");
}
__device__ __forceinline__ void tma_ld_s(u32 d, const CUtensorMap* m, int c0, int c1, u32 b) {
    asm volatile("cp.async.bulk.tensor.2d.shared::cluster.global.mbarrier::complete_tx::bytes.L2::cache_hint [%0], [%1, {%3,%4}], [%2], %5;" ::"r"(d), "l"(m), "r"(b), "r"(c0), "r"(c1), "l"(pol_stream()) : "memory");
}
__device__ __forceinline__ void tma_st(const CUtensorMap* m, u32 s, int c0, int c1) {
    asm volatile("cp.async.bulk.tensor.2d.global.shared::cta.bulk_group [%0, {%2,%3}], [%1];" ::"l"(m), "r"(s), "r"(c0), "r"(c1) : "memory");
}
__device__ __forceinline__ void bulk_commit() { asm volatile("cp.async.bulk.commit_group;" ::: "memory"); }
__device__ __forceinline__ void bulk_wait() { asm volatile("cp.async.bulk.wait_group 0;" ::: "memory"); }
__device__ __forceinline__ void fence_async() { asm volatile("fence.proxy.async.shared::cta;" ::: "memory"); }
__device__ __forceinline__ void red_add(u32* c) { asm volatile("red.relaxed.gpu.global.add.u32 [%0], 1;" ::"l"(c) : "memory"); }
__device__ __forceinline__ u32 ld_rlx(const u32* c) { u32 v; asm volatile("ld.relaxed.gpu.global.u32 %0, [%1];" : "=r"(v) : "l"(c) : "memory"); return v; }
__device__ __forceinline__ void st_rlx(u32* c, u32 v) { asm volatile("st.relaxed.gpu.global.u32 [%0], %1;" ::"l"(c), "r"(v) : "memory"); }
__device__ __forceinline__ uint2 ld_rlx64(const uint2* c) { u64 v; asm volatile("ld.relaxed.gpu.global.b64 %0, [%1];" : "=l"(v) : "l"(c) : "memory"); return make_uint2((u32)v, (u32)(v >> 32)); }
__device__ __forceinline__ void st_rlx64(uint2* c, u32 x, u32 y) { asm volatile("st.relaxed.gpu.global.b64 [%0], %1;" ::"l"(c), "l"((u64)x | ((u64)y << 32)) : "memory"); }
__device__ __forceinline__ uint4 ld_rlx128(const uint4* c) {
    u64 a, b;
    asm volatile("{.reg .b128 r; ld.relaxed.gpu.global.b128 r, [%2]; mov.b128 {%0,%1}, r;}" : "=l"(a), "=l"(b) : "l"(c) : "memory");
    return make_uint4((u32)a, (u32)(a >> 32), (u32)b, (u32)(b >> 32));
}
__device__ __forceinline__ void st_rlx128(uint4* c, u32 x, u32 y, u32 z, u32 w) {
    asm volatile("{.reg .b128 r; mov.b128 r, {%1,%2}; st.relaxed.gpu.global.b128 [%0], r;}" ::"l"(c), "l"((u64)x | ((u64)y << 32)), "l"((u64)z | ((u64)w << 32)) : "memory");
}
__device__ __forceinline__ void poll_cnt(const u32* c, u32 tgt) {
#pragma unroll 1
    for (int i = 0; i < SPIN_LIMIT; i++) {
        const u32 v = ld_rlx(c);
        if ((int)(v - tgt) >= 0) return;
    }
}
__device__ __forceinline__ u32 clk() { u32 c; asm volatile("mov.u32 %0, %clock;" : "=r"(c)); return c; }
__device__ __forceinline__ void cbar() { asm volatile("bar.sync 1, 256;" ::: "memory"); }
__device__ __forceinline__ void ldsm4(u32* r, u32 a) { asm volatile("ldmatrix.sync.aligned.m8n8.x4.shared.b16 {%0,%1,%2,%3}, [%4];" : "=r"(r[0]), "=r"(r[1]), "=r"(r[2]), "=r"(r[3]) : "r"(a) : "memory"); }
__device__ __forceinline__ void ldsm4t(u32* r, u32 a) { asm volatile("ldmatrix.sync.aligned.m8n8.x4.trans.shared.b16 {%0,%1,%2,%3}, [%4];" : "=r"(r[0]), "=r"(r[1]), "=r"(r[2]), "=r"(r[3]) : "r"(a) : "memory"); }
__device__ __forceinline__ void stsm4(u32 a, u32 r0, u32 r1, u32 r2, u32 r3) { asm volatile("stmatrix.sync.aligned.m8n8.x4.shared.b16 [%0], {%1,%2,%3,%4};" ::"r"(a), "r"(r0), "r"(r1), "r"(r2), "r"(r3) : "memory"); }
__device__ __forceinline__ void stsm4t(u32 a, u32 r0, u32 r1, u32 r2, u32 r3) { asm volatile("stmatrix.sync.aligned.m8n8.x4.trans.shared.b16 [%0], {%1,%2,%3,%4};" ::"r"(a), "r"(r0), "r"(r1), "r"(r2), "r"(r3) : "memory"); }
__device__ __forceinline__ uint4 lds128(u32 a) { uint4 v; asm volatile("ld.shared.v4.u32 {%0,%1,%2,%3}, [%4];" : "=r"(v.x), "=r"(v.y), "=r"(v.z), "=r"(v.w) : "r"(a) : "memory"); return v; }
__device__ __forceinline__ uint2 lds64(u32 a) { uint2 v; asm volatile("ld.shared.v2.u32 {%0,%1}, [%2];" : "=r"(v.x), "=r"(v.y) : "r"(a) : "memory"); return v; }
__device__ __forceinline__ u32 lds32(u32 a) { u32 v; asm volatile("ld.shared.u32 %0, [%1];" : "=r"(v) : "r"(a) : "memory"); return v; }
__device__ __forceinline__ u32 lds16(u32 a) { unsigned short v; asm volatile("ld.shared.u16 %0, [%1];" : "=h"(v) : "r"(a) : "memory"); return v; }
__device__ __forceinline__ void sts128(u32 a, u32 x, u32 y, u32 z, u32 w) { asm volatile("st.shared.v4.u32 [%0], {%1,%2,%3,%4};" ::"r"(a), "r"(x), "r"(y), "r"(z), "r"(w) : "memory"); }
__device__ __forceinline__ void sts32(u32 a, u32 x) { asm volatile("st.shared.u32 [%0], %1;" ::"r"(a), "r"(x) : "memory"); }
__device__ __forceinline__ void sts16(u32 a, u32 x) { asm volatile("st.shared.u16 [%0], %1;" ::"r"(a), "h"((unsigned short)x) : "memory"); }
__device__ __forceinline__ void sts16p(bool p, u32 a, u32 x) { asm volatile("{.reg .pred p; setp.ne.u32 p, %2, 0; @p st.shared.u16 [%0], %1;}" ::"r"(a), "h"((unsigned short)x), "r"((u32)p) : "memory"); }
__device__ __forceinline__ void mma(float* d, const u32* a, u32 b0, u32 b1) {
    asm("mma.sync.aligned.m16n8k16.row.col.f32.f16.f16.f32 {%0,%1,%2,%3}, {%4,%5,%6,%7}, {%8,%9}, {%0,%1,%2,%3};"
        : "+f"(d[0]), "+f"(d[1]), "+f"(d[2]), "+f"(d[3]) : "r"(a[0]), "r"(a[1]), "r"(a[2]), "r"(a[3]), "r"(b0), "r"(b1));
}
__device__ __forceinline__ void mma0(float* d, const u32* a, u32 b0, u32 b1) {
    asm("mma.sync.aligned.m16n8k16.row.col.f32.f16.f16.f32 {%0,%1,%2,%3}, {%4,%5,%6,%7}, {%8,%9}, {%10,%10,%10,%10};"
        : "=f"(d[0]), "=f"(d[1]), "=f"(d[2]), "=f"(d[3]) : "r"(a[0]), "r"(a[1]), "r"(a[2]), "r"(a[3]), "r"(b0), "r"(b1), "f"(0.f));
}
__device__ __forceinline__ void hmma(u32* d, const u32* a, u32 b0, u32 b1) {
    asm("mma.sync.aligned.m16n8k16.row.col.f16.f16.f16.f16 {%0,%1}, {%2,%3,%4,%5}, {%6,%7}, {%0,%1};"
        : "+r"(d[0]), "+r"(d[1]) : "r"(a[0]), "r"(a[1]), "r"(a[2]), "r"(a[3]), "r"(b0), "r"(b1));
}
__device__ __forceinline__ void hmma0(u32* d, const u32* a, u32 b0, u32 b1) {
    asm("mma.sync.aligned.m16n8k16.row.col.f16.f16.f16.f16 {%0,%1}, {%2,%3,%4,%5}, {%6,%7}, {%8,%8};"
        : "=r"(d[0]), "=r"(d[1]) : "r"(a[0]), "r"(a[1]), "r"(a[2]), "r"(a[3]), "r"(b0), "r"(b1), "r"(0u));
}
__device__ __forceinline__ u32 ptag(u32 v, u32 tag) { return (v & ~1u) | (tag & 1u); }
__device__ __forceinline__ u32 plo(u32 a, u32 b) { return __byte_perm(a, b, 0x5410); }
__device__ __forceinline__ u32 phi(u32 a, u32 b) { return __byte_perm(a, b, 0x7632); }
__device__ __forceinline__ void mmab(float* d, u32 a0, u32 a1, u32 a2, u32 a3, u32 b0, u32 b1) {
    asm("mma.sync.aligned.m16n8k16.row.col.f32.bf16.bf16.f32 {%0,%1,%2,%3}, {%4,%5,%6,%7}, {%8,%9}, {%0,%1,%2,%3};"
        : "+f"(d[0]), "+f"(d[1]), "+f"(d[2]), "+f"(d[3]) : "r"(a0), "r"(a1), "r"(a2), "r"(a3), "r"(b0), "r"(b1));
}
__device__ __forceinline__ u32 pk(float lo, float hi) { u32 r; asm("cvt.rn.f16x2.f32 %0, %1, %2;" : "=r"(r) : "f"(hi), "f"(lo)); return r; }
__device__ __forceinline__ u32 pkb(float lo, float hi) { u32 r; asm("cvt.rn.bf16x2.f32 %0, %1, %2;" : "=r"(r) : "f"(hi), "f"(lo)); return r; }
__device__ __forceinline__ float blo(u32 v) { return __uint_as_float(v << 16); }
__device__ __forceinline__ float bhi(u32 v) { return __uint_as_float(v & 0xffff0000u); }
__device__ __forceinline__ float rbf(float v) { return __bfloat162float(__float2bfloat16_rn(v)); }
__device__ __forceinline__ u32 hadd(u32 a, u32 b) { u32 r; asm("add.rn.f16x2 %0, %1, %2;" : "=r"(r) : "r"(a), "r"(b)); return r; }
__device__ __forceinline__ u32 hsub(u32 a, u32 b) { u32 r; asm("sub.rn.f16x2 %0, %1, %2;" : "=r"(r) : "r"(a), "r"(b)); return r; }
__device__ __forceinline__ u32 hmul(u32 a, u32 b) { u32 r; asm("mul.rn.f16x2 %0, %1, %2;" : "=r"(r) : "r"(a), "r"(b)); return r; }
__device__ __forceinline__ u32 hfma(u32 a, u32 b, u32 c) { u32 r; asm("fma.rn.f16x2 %0, %1, %2, %3;" : "=r"(r) : "r"(a), "r"(b), "r"(c)); return r; }
__device__ __forceinline__ u32 hfms(u32 a, u32 b, u32 c) { u32 r; asm("{.reg .b32 n; neg.f16x2 n, %3; fma.rn.f16x2 %0, %1, %2, n;}" : "=r"(r) : "r"(a), "r"(b), "r"(c)); return r; }
__device__ __forceinline__ u32 badd(u32 a, u32 b) { u32 r; asm("add.rn.bf16x2 %0, %1, %2;" : "=r"(r) : "r"(a), "r"(b)); return r; }
__device__ __forceinline__ u32 bfma(u32 a, u32 b, u32 c) { u32 r; asm("fma.rn.bf16x2 %0, %1, %2, %3;" : "=r"(r) : "r"(a), "r"(b), "r"(c)); return r; }
__device__ __forceinline__ u32 bsub(u32 a, u32 b) { u32 r; asm("sub.rn.bf16x2 %0, %1, %2;" : "=r"(r) : "r"(a), "r"(b)); return r; }
__device__ __forceinline__ void cmul(u32& re, u32& im, u32 c, u32 s) {
    u32 r = hfms(re, c, hmul(im, s));
    im = hfma(re, s, hmul(im, c));
    re = r;
}
__device__ __forceinline__ void wpow(int n, float& c, float& s) {
    int m = (n << 21) >> 21;
    float x = (float)m * (-6.283185307179586f / 2048.f);
    c = __cosf(x); s = __sinf(x);
}
__device__ __forceinline__ int kap(int p, int m) { int g = m & 7; return m < 8 ? 2 * g + p : ((g | p) == 0 ? 16 : 32 - 2 * g - p); }
__device__ __forceinline__ int fsw(int a) { return ((a ^ (a >> 2)) & 1) | ((a >> 2) & 2) | ((((a >> 4) ^ (a >> 1)) & 1) << 2); }
__device__ __forceinline__ int ssw(int k1) { return ((k1 & 1) << 2) | (k1 & 2); }
__device__ __forceinline__ u32 tword(u32 tb, int R, int lane) { return tb + (((R >> 2) * 32 + lane) << 4) + ((R & 3) << 2); }
template <int N> __device__ __forceinline__ void tload(u32* r, u32 tb, int R0, int lane) {
#pragma unroll
    for (int i = 0; i < N / 4; i++) { uint4 v = lds128(tb + (((R0 / 4 + i) * 32 + lane) << 4)); r[4 * i] = v.x; r[4 * i + 1] = v.y; r[4 * i + 2] = v.z; r[4 * i + 3] = v.w; }
}
__device__ __forceinline__ void tpair(u32 tb, int lane, int n0, int n1, float sc, int Rc, int Rs, int Rn) {
    float c0, s0, c1, s1;
    wpow(n0, c0, s0); wpow(n1, c1, s1);
    sts32(tword(tb, Rc, lane), pk(c0 * sc, c1 * sc));
    sts32(tword(tb, Rs, lane), pk(s0 * sc, s1 * sc));
    if (Rn >= 0) sts32(tword(tb, Rn, lane), pk(-s0 * sc, -s1 * sc));
}
__device__ __forceinline__ void ln_finish(float (&s)[2], float (&q)[2], float (&mean)[2], float (&rstd)[2]) {
#pragma unroll
    for (int o = 1; o < 32; o <<= 1)
#pragma unroll
        for (int c = 0; c < 2; c++) { s[c] += __shfl_xor_sync(~0u, s[c], o); q[c] += __shfl_xor_sync(~0u, q[c], o); }
#pragma unroll
    for (int c = 0; c < 2; c++) {
        float m = s[c] * (1.f / 1024.f), var = fmaxf(fmaf(-m, m, q[c] * (1.f / 1024.f)), 0.f), sd;
        asm("sqrt.approx.f32 %0, %1;" : "=f"(sd) : "f"(rbf(rbf(var) + 1e-5f)));
        asm("rcp.approx.f32 %0, %1;" : "=f"(rstd[c]) : "f"(rbf(sd)));
        mean[c] = rbf(m);
    }
}

__device__ __forceinline__ void p2_tables(u32 tb, int warp, int lane) {
    int g = lane >> 2, t = lane & 3, s = warp >> 2, r = warp & 3;
    float c, sn;
    wpow(128 * (g + 8 * (r & 1)) * (t + 4 * (r >> 1) + 8 * s), c, sn);
    c *= 0.25f; sn *= 0.25f;
    sts32(tword(tb, s * 4 + r, lane), pk(c, -sn));
    sts32(tword(tb, 8 + s * 4 + r, lane), pk(sn, c));
    if (warp < 4) { int m = g + 8 * (r & 1), k = 2 * t + 8 * (r >> 1); tpair(tb, lane, 128 * m * k, 128 * m * (k + 1), 0.25f, 16 + r, 20 + r, 24 + r); }
    else if (warp < 6) { int q1 = g + 8 * (warp - 4); tpair(tb, lane, 16 * q1 * 2 * t, 16 * q1 * (2 * t + 1), 1.f, 32 + warp - 4, 34 + warp - 4, -1); }
    else { int q1 = 8 * (warp - 6) + 2 * t; tpair(tb, lane, -16 * g * q1, -16 * g * (q1 + 1), 1.f, 36 + warp - 6, 38 + warp - 6, -1); }
    if (warp == 7) tpair(tb, lane, 256 * g * 2 * t, 256 * g * (2 * t + 1), 0.25f, 28, 29, 30);
}
__device__ __forceinline__ void p3_tables(u32 TB, int a, int warp, int lane) {
    const int g = lane >> 2, t = lane & 3;
        {
            int p = warp >> 2, q = warp & 3;
#pragma unroll
            for (int ga = 0; ga < 2; ga++) { int d0 = g + 8 * ga + 16 * (q & 1), m = 8 * (q >> 1) + 2 * t; tpair(TB, lane, -2 * d0 * kap(p, m), -2 * d0 * kap(p, m + 1), 0.5f, warp * 2 + ga, 16 + warp * 2 + ga, -1); }
            { int m = g + 8 * (q & 1), k = 2 * t + 8 * (q >> 1); tpair(TB, lane, -64 * m * kap(p, k), -64 * m * kap(p, k + 1), 0.25f, 32 + 12 * p + q, 36 + 12 * p + q, 40 + 12 * p + q); }
            int kh = warp & 1, s = (warp >> 1) & 1, M = warp >> 2, k1 = t + 4 * kh + 8 * s;
            float c, sn;
            wpow(k1 * (a + 128 * g) + (((k1 ^ M) & 1) ? -256 : 256), c, sn);
            const float sc = 0.5f * 0.70710678118654752f;
            c *= sc; sn *= sc;
            sts32(tword(TB, 56 + M * 8 + s * 4 + 2 * kh, lane), pk(c, sn));
            sts32(tword(TB, 56 + M * 8 + s * 4 + 2 * kh + 1, lane), M ? pk(sn, -c) : pk(-sn, c));
        }
}
template <int NC> __device__ __forceinline__ void p2_core(const u32 (&d)[4][NC], u32 (&o)[4][NC], const u32* T, const u32 (&wr)[NC][2], const u32 (&wi)[NC][2]) {
    const u32 AG[4] = {T[28], T[30], T[29], T[28]};
#pragma unroll
    for (int i = 0; i < NC; i++) {
        u32 A[4], y[2], z[2], p[2], q[2];
        hmma0(A, T + 0, d[0][i], d[1][i]); hmma0(A + 2, T + 8, d[0][i], d[1][i]);
        hmma(A, T + 4, d[2][i], d[3][i]); hmma(A + 2, T + 12, d[2][i], d[3][i]);
        cmul(A[0], A[2], T[32], T[34]); cmul(A[1], A[3], T[33], T[35]);
        hmma0(y, A, T[28], T[30]); hmma0(z, A, T[29], T[28]);
        cmul(y[0], z[0], wr[i][0], wi[i][0]); cmul(y[1], z[1], wr[i][1], wi[i][1]);
        hmma0(p, AG, y[0], z[0]); hmma0(q, AG, y[1], z[1]);
        cmul(p[0], p[1], T[36], T[38]); cmul(q[0], q[1], T[37], T[39]);
        hmma0(y, T + 16, p[0], q[0]); hmma0(z, T + 24, p[0], q[0]);
        hmma(y, T + 20, p[1], q[1]); hmma(z, T + 16, p[1], q[1]);
        o[0][i] = plo(y[0], z[0]); o[1][i] = phi(y[0], z[0]); o[2][i] = plo(y[1], z[1]); o[3][i] = phi(y[1], z[1]);
    }
}
template <int N> __device__ __forceinline__ void w_scale(u32* w, u32 mi, int warp, int lane, u32 tag) {
    u32 mx = 0;
#pragma unroll
    for (int i = 0; i < N; i++) mx = __vmaxu2(mx, w[i] & 0x7fff7fffu);
    mx = __reduce_max_sync(~0u, max(mx & 0xffffu, mx >> 16));
    if (lane == 0) sts32(mi + MI_WMAX + warp * 4, mx);
    cbar();
    uint4 m0 = lds128(mi + MI_WMAX), m1 = lds128(mi + MI_WMAX + 16);
    mx = max(max(max(m0.x, m0.y), max(m0.z, m0.w)), max(max(m1.x, m1.y), max(m1.z, m1.w)));
    u32 E = min(max(mx >> 7, 2u), 253u);
    if (threadIdx.x == 0) st_rlx(&g_exp[blockIdx.x], (tag << 8) | E);
    const u32 sc = ((255u - E) << 7) * 0x10001u;
#pragma unroll
    for (int i = 0; i < N; i++) { const u32 v = bfma(w[i], sc, 0x80008000u); w[i] = pk(blo(v), bhi(v)); }
}

struct Maps { CUtensorMap out, wr, wi, g, u, e1, e2; };
struct Ptrs { const char *wr, *wi, *wg, *wu, *wd; };

__global__ void __launch_bounds__(384, 1)
fused_kernel(const __grid_constant__ Maps mp, const __nv_bfloat16* __restrict__ gx,
             const __nv_bfloat16* __restrict__ grt, const Ptrs pw, __nv_bfloat16* __restrict__ out) {
    extern __shared__ __align__(1024) unsigned char smem[];
    const int a = blockIdx.x, tid = threadIdx.x, warp = tid >> 5, lane = tid & 31;
    const u32 sb = su(smem), R0 = sb + SM_R0, R1 = sb + SM_R1, R2 = sb + SM_R2, TB = sb + SM_TB, MI = sb + SM_MI;
    const u32 BR = MI + MI_BAR;
    STAMP_BEGIN();
    if (warp < 8) {
#pragma unroll
        for (int i = 0; i < 8; i++) {
            int b = warp + 8 * (i >> 2), ch = (i & 3) * 32 + lane;
            asm volatile("cp.async.cg.shared.global.L2::cache_hint [%0], [%1], 16, %2;" ::"r"(R0 + b * 2048 + ((ch ^ ((ch >> 3) & 7)) << 4)), "l"(gx + (size_t)(a + 128 * b) * 1024 + ch * 8), "l"(pol_stream()) : "memory");
        }
        asm volatile("cp.async.commit_group;" ::: "memory");
        STAMP(5);
    }
    if (warp >= 8) {
        asm volatile("setmaxnreg.dec.sync.aligned.u32 40;");
        if (tid == 256) STAMPX(13);
        if (tid == 256) {
#pragma unroll
            for (int i = 0; i < B_NUM; i++)
                mb_init(BR + 8 * i, (i == B_ST || i == B_ST + 1 || i == B_XF || i == B_FREE || i == B_FREE + 1) ? 8 : (i == B_WD ? 2 : 1));
            fence_async();
        }
        asm volatile("bar.sync 3, 128;" ::: "memory");
        asm volatile("bar.arrive 0, 384;" ::: "memory");
        if (tid == 256) STAMPX(17);
        if (warp == 8) {
            const u32 t0 = clk();
#pragma unroll 1
            for (int it = 0; it < SPIN_LIMIT && clk() - t0 < WAITX; it++) {}
        }
        if (warp == 11) {
            const u32 ep = ld_rlx((const u32*)&g_best.y) >> 7;
            if (lane == 0) { sts32(MI + MI_RUN + 4, 0); st_rlx64(&g_key[a], 0, 0); st_rlx(&g_exp[a], 0); }
            if (lane < 16) st_rlx64(&g_E1x[lane * 128 + a], 0, 0);
            if (a >= 112)
#pragma unroll 1
                for (int i = 0; i < 4; i++) st_rlx64(&g_E2x[(i * 32 + lane) * 16 + a - 112], 0, 0);
            __syncwarp();
            if (lane == 0) { sts32(MI + MI_TAG, ep + 1); mb_arrive(BR + 8 * B_TAG); }
            mb_wait(BR + 8 * B_XF, 0);
#pragma unroll 1
            for (int i = 0; i < 8; i++) {
                st_rlx128(&g_candN[a * 256 + i * 32 + lane], 0, 0, ep, 0);
                st_rlx128(&g_candH[a * 256 + i * 32 + lane], 0, 0, ep, 0);
                if (a < 112) st_rlx128(&g_part[a * 256 + i * 32 + lane], ep & 255u, 0, 0, 0);
            }
            __syncwarp();
            const u32 tag = ep + 1;
            mb_wait(BR + 8 * B_ST, 0);
#pragma unroll 1
            for (int v = 0; v < 8; v++) p2_tables(TB + 9216, v, lane);
            __syncwarp();
            if (lane == 0) mb_arrive(BR + 8 * B_T2);
#pragma unroll 1
            for (int v = 0; v < 8; v++) p3_tables(TB, a, v, lane);
            mb_wait(BR + 8 * B_ST, 1);
#pragma unroll 1
            for (int it = 0; it < SPIN_LIMIT; it++) {
                uint4 v = ld_rlx128((const uint4*)g_exp + lane);
                const u32 tg = tag & 0xffffffu;
                bool ok = (v.x >> 8) == tg && (v.y >> 8) == tg && (v.z >> 8) == tg && (v.w >> 8) == tg;
                v.x &= 255u; v.y &= 255u; v.z &= 255u; v.w &= 255u;
                u32 em = __reduce_max_sync(~0u, max(max(v.x, v.y), max(v.z, v.w)));
                sts32(MI + MI_EXP + lane * 4, v.x | (v.y << 8) | (v.z << 16) | (v.w << 24));
                if (lane == 0) sts32(MI + MI_EXP + 128, em);
                if (__all_sync(~0u, ok)) break;
            }
            __syncwarp();
            if (lane == 0) mb_arrive(BR + 8 * B_T3);
            if (lane < 8 && a < 112) {
                mb_wait(BR + 8 * (B_FREE + 1), 0);
                mb_wait(BR + 8 * B_E2, 0);
                fence_async();
                if (lane == 0) mb_expect(BR + 8 * B_WD, 16384);
                __syncwarp(0xffu);
                bulk_g2s_s(R1 + (24 + lane) * 2064, pw.wd + (size_t)(a * 32 + 24 + lane) * 2048, 2048, BR + 8 * B_WD);
            }
            __syncwarp();
            asm volatile("bar.sync 2, 288;" ::: "memory");
            {
                const u32 ck = __reduce_max_sync(~0u, lds32(MI + MI_KEYS + (lane & 7) * 4));
                if (lane == 0) {
                    asm volatile("red.relaxed.gpu.global.max.u64 [%0], %1;" ::"l"(&g_best.x), "l"(((u64)tag << 32) | ck) : "memory");
                    red_add((u32*)&g_best.y);
                    st_rlx64(&g_key[a], ck, tag);
                }
                __syncwarp();
            }
            if (lane == 0) {
#pragma unroll 1
                for (int it = 0; it < SPIN_LIMIT; it++) {
                    const uint4 v = ld_rlx128((const uint4*)&g_best);
                    const bool fin = (int)(v.z - tag * 128) >= 0;
                    if (fin) asm volatile("st.volatile.shared.v2.u32 [%0], {%1, %2};" ::"r"(MI + MI_RUN), "r"(v.x), "r"(fin ? 2u : 1u) : "memory");
                    if (fin) break;
                }
            }
            __syncwarp();
#pragma unroll 1
            for (int it = 0; it < SPIN_LIMIT; it++) {
                uint4 v0 = ld_rlx128((const uint4*)g_key + lane), v1 = ld_rlx128((const uint4*)g_key + 32 + lane);
                u32 k2 = __reduce_max_sync(~0u, max(max(v0.x, v0.z), max(v1.x, v1.z)));
                if (lane == 0) sts32(MI + MI_GK + 4, k2);
                if (__all_sync(~0u, v0.y == tag && v0.w == tag && v1.y == tag && v1.w == tag)) break;
            }
            if (lane == 0) mb_arrive(BR + 8 * B_TAG);
        }
        if (lane == 0) {
            if (warp == 8) {
                const int wc0 = ((a & 15) * 513 + (a >> 4) * 64) & ~7;
                const bool ffn = a < 112;
                mb_expect(BR + 8 * B_W, 36864);
                tma_ld_s(R1, &mp.wr, wc0, 0, BR + 8 * B_W);
                tma_ld_s(R1 + 18432, &mp.wi, wc0, 0, BR + 8 * B_W);
                if (ffn) {
                    int done = 0;
#pragma unroll 1
                    for (int i = 0; i < 22; i++) {
                        const int dep = i < NSW1 ? DEPA : (i < NSW2 ? DEPB : DEPC);
#pragma unroll 1
                        for (; done <= i - dep; done++) { mb_wait(BR + 8 * (B_RING + (done & 7)), (done >> 3) & 1); if (done == 15) mb_arrive(BR + 8 * B_GU); }
                        const u32 bb = BR + 8 * (B_RING + (i & 7));
                        if (i < 16) { mb_expect(bb, 8192); tma_ld_s(R2 + i * 8192, (i & 1) ? &mp.u : &mp.g, a * 32, (i >> 1) * 128, bb); }
                        else {
                            if (i == 16) { mb_wait(BR + 8 * B_FREE, 0); fence_async(); }
                            mb_expect(bb, 8192);
#pragma unroll 1
                            for (int r = (i - 16) * 4; r < (i - 16) * 4 + 4; r++) bulk_g2s_s(R1 + r * 2064, pw.wd + (size_t)(a * 32 + r) * 2048, 2048, bb);
                        }
                    }
#pragma unroll 1
                    for (; done < 22; done++) { mb_wait(BR + 8 * (B_RING + (done & 7)), (done >> 3) & 1); if (done == 15) mb_arrive(BR + 8 * B_GU); }
                    mb_arrive(BR + 8 * B_WD);
                }
                STAMPX(16);
            } else if (warp <= 10) {
                const int h = warp - 9;
                const u32 buf = R0 + h * 16384;
                const u32 tg0 = (ld_rlx(&g_cnt[h * 64]) & ~127u) + 128, tg1 = (ld_rlx(&g_cnt[(2 + h) * 64]) & ~127u) + 128;
#pragma unroll 1
                for (int q = 0; q < 2; q++) {
                    mb_wait(BR + 8 * (B_ST + h), q);
                    fence_async();
                    if (h) mb_wait(BR + 8 * B_G, q);
                    tma_st(q ? &mp.e2 : &mp.e1, buf, a * 32, h * 128); bulk_commit();
                    if (ACKW) bulk_wait(); else asm volatile("cp.async.bulk.wait_group.read 0;" ::: "memory");
                    red_add(&g_cnt[(2 * q + h) * 64]);
                    if (!h) mb_arrive(BR + 8 * B_G);
                    STAMPX(h ? 3 + 4 * q : 25 + 2 * q);
                    __nanosleep(PDELAY);
                    poll_cnt(&g_cnt[(2 * q + h) * 64], q ? tg1 : tg0);
                    STAMPX(h ? 4 + 4 * q : 26 + 3 * q);
                                        const uint4* src = (q ? g_E2 : g_E1) + (h * 128 + a) * 1024;
                    mb_expect(BR + 8 * (B_LD + h), 16384);
                    bulk_g2s(buf, src, 8192, BR + 8 * (B_LD + h));
                    bulk_g2s(buf + 8192, src + 512, 8192, BR + 8 * (B_LD + h));
                }
                if (h) { mb_wait(BR + 8 * (B_LD + 1), 1); mb_arrive(BR + 8 * B_E2); }
                if (h == 0) {
                    mb_wait(BR + 8 * B_ST, 0);
                    fence_async();
                    const uint4 k0 = lds128(MI + MI_KEYS), k1 = lds128(MI + MI_KEYS + 16);
                    const int crow = 2047 - (int)(max(max(max(k0.x, k0.y), max(k0.z, k0.w)), max(max(k1.x, k1.y), max(k1.z, k1.w))) & 0xffffu);
#pragma unroll 1
                    for (int b = 0; b < 16; b++) if (a + 128 * b != crow) tma_st(&mp.out, R0 + b * 2048, 0, (a + 128 * b) * 16);
                    mb_wait(BR + 8 * B_TAG, 1);
                    if (crow != 2047 - (int)(lds32(MI + MI_GK + 4) & 0xffffu)) tma_st(&mp.out, R0 + (crow >> 7) * 2048, 0, crow * 16);
                    bulk_commit();
                    asm volatile("cp.async.bulk.wait_group.read 0;" ::: "memory");
                }
            }
        }
        return;
    }
    const int g = lane >> 2, t = lane & 3;

    const int fa = fsw(a);
    const u32 xo = (lane >> 1) * 128;
    const int xs = (lane >> 1) & 7, xh = (lane & 1) * 4;
    u32 za[2][2];
    {
        int n = lane & 7, rho = (lane >> 3) & 1, im = lane >> 4;
#pragma unroll
        for (int pp = 0; pp < 2; pp++) {
            int k0 = 2 * n + pp;
            za[pp][0] = R0 + (k0 & 1) * 512 + (k0 >> 1) * 2048 + rho * 1024 + im * 128 + ((warp ^ (k0 >> 1)) << 4);
            k0 = (2 * n + pp - 1) & 15;
            za[pp][1] = R0 + (k0 & 1) * 512 + (k0 >> 1) * 2048 + (1 - rho) * 1024 + (2 + im) * 128 + ((warp ^ (k0 >> 1)) << 4);
        }
    }
    u32 tag;
    u32 hh[2][16];
    {
        STAMP(10);
        {
            int p = warp >> 2, q = warp & 3;
#pragma unroll
            for (int rho = 0; rho < 2; rho++) { int kp = kap(p, 8 * rho + g), d0 = 8 * q + 2 * t; tpair(TB, lane, 2 * d0 * kp, 2 * (d0 + 1) * kp, 0.5f, warp * 2 + rho, 16 + warp * 2 + rho, -1); }
            { int kp = kap(p, g + 8 * (q & 1)), k = 2 * t + 8 * (q >> 1); tpair(TB, lane, 64 * k * kp, 64 * (k + 1) * kp, 0.25f, 32 + 12 * p + q, 36 + 12 * p + q, 40 + 12 * p + q); }
            int rho = warp & 1, s = (warp >> 1) & 1, M = warp >> 2, k1 = g + 8 * rho;
            int off = ((k1 ^ s) & 1) ? -256 : 256;
            float c0, s0, c1, s1;
            wpow(k1 * (a + 256 * t) + off, c0, s0); wpow(k1 * (a + 256 * t + 128) + off, c1, s1);
            const float sc = 0.25f * 0.70710678118654752f;
            u32 wc = pk(c0 * sc, c1 * sc), ws = pk(s0 * sc, s1 * sc);
            u32 lo = M ? ws : wc, hi = M ? wc : ws;
            if (M == s) hi ^= 0x80008000u;
            sts32(tword(TB, 56 + M * 8 + s * 4 + rho, lane), lo);
            sts32(tword(TB, 56 + M * 8 + s * 4 + rho + 2, lane), hi);
        }
        asm volatile("bar.sync 0, 384;" ::: "memory");
        asm volatile("setmaxnreg.inc.sync.aligned.u32 232;");
        u32 T[56]; tload<56>(T, TB, 0, lane);
        STAMP(23);
        asm volatile("cp.async.wait_group 0;" ::: "memory");
        __syncwarp();
        STAMP(1);
        u32 u[2][2][4][2];
        {
            float f[2][2][16], sm[2], sq[2], mean[2], rstd[2];
#pragma unroll
            for (int c = 0; c < 2; c++) {
                u32 x[16];
#pragma unroll
                for (int jn = 0; jn < 4; jn++) ldsm4t(x + 4 * jn, R0 + (warp + 8 * c) * 2048 + xo + (((xh + jn) ^ xs) << 4));
                float s0 = 0.f, s1 = 0.f, q0 = 0.f, q1 = 0.f, q2 = 0.f, q3 = 0.f;
#pragma unroll
                for (int i = 0; i < 8; i++) {
                    const u32 p = x[4 * (i >> 1) + (i & 1)], q = x[4 * (i >> 1) + 2 + (i & 1)];
                    float a0 = blo(p) + blo(q), a1 = bhi(p) + bhi(q), b0 = blo(p) - blo(q), b1 = bhi(p) - bhi(q);
                    f[c][0][2 * i] = a0; f[c][0][2 * i + 1] = a1; f[c][1][2 * i] = b0; f[c][1][2 * i + 1] = b1;
                    s0 += a0; s1 += a1; q0 = fmaf(a0, a0, q0); q1 = fmaf(a1, a1, q1); q2 = fmaf(b0, b0, q2); q3 = fmaf(b1, b1, q3);
                }
                sm[c] = s0 + s1; sq[c] = 0.5f * ((q0 + q1) + (q2 + q3));
            }
#pragma unroll
            for (int c = 0; c < 2; c++)
#pragma unroll
                for (int jn = 0; jn < 4; jn++) { u32 q[4]; ldsm4(q, R0 + (warp + 8 * c) * 2048 + xo + (((xh + jn) ^ xs) << 4)); hh[c][jn] = q[0]; hh[c][4 + jn] = q[1]; hh[c][8 + jn] = q[2]; hh[c][12 + jn] = q[3]; }
            __syncwarp();
            if (lane == 0) mb_arrive(BR + 8 * B_XF);
            ln_finish(sm, sq, mean, rstd);
#pragma unroll
            for (int c = 0; c < 2; c++) {
                const float r = rstd[c], mr = -2.f * mean[c] * r;
#pragma unroll
                for (int i = 0; i < 8; i++) {
                    u[0][c][i >> 1][i & 1] = pk(fmaf(f[c][0][2 * i], r, mr), fmaf(f[c][0][2 * i + 1], r, mr));
                    u[1][c][i >> 1][i & 1] = pk(f[c][1][2 * i] * r, f[c][1][2 * i + 1] * r);
                }
            }
        }
        u32 Ab[16]; tload<16>(Ab, TB, 56, lane);
#pragma unroll
        for (int p = 0; p < 2; p++) {
            const u32 *Ar = T + 32 + 12 * p, *Ai = Ar + 4, *An = Ar + 8;
            u32 tr[4][2], ti[4][2], z[2][2][4];
#pragma unroll
            for (int jn = 0; jn < 4; jn++) {
                hmma0(tr[jn], Ar, u[p][0][jn][0], u[p][0][jn][1]); hmma0(ti[jn], Ai, u[p][0][jn][0], u[p][0][jn][1]);
                hmma(tr[jn], An, u[p][1][jn][0], u[p][1][jn][1]); hmma(ti[jn], Ar, u[p][1][jn][0], u[p][1][jn][1]);
#pragma unroll
                for (int r = 0; r < 2; r++) cmul(tr[jn][r], ti[jn][r], T[(p * 4 + jn) * 2 + r], T[16 + (p * 4 + jn) * 2 + r]);
            }
#pragma unroll
            for (int pp = 0; pp < 2; pp++) {
                const u32 *Br = T + 32 + 12 * pp, *Bi = Br + 4, *Bn = Br + 8;
                u32 vr[4], vi[4];
#pragma unroll
                for (int r = 0; r < 4; r++) {
                    vr[r] = pp ? hsub(tr[r >> 1][r & 1], tr[2 + (r >> 1)][r & 1]) : hadd(tr[r >> 1][r & 1], tr[2 + (r >> 1)][r & 1]);
                    vi[r] = pp ? hsub(ti[r >> 1][r & 1], ti[2 + (r >> 1)][r & 1]) : hadd(ti[r >> 1][r & 1], ti[2 + (r >> 1)][r & 1]);
                }
#pragma unroll
                for (int jq = 0; jq < 2; jq++) {
                    hmma0(z[pp][jq], vr, Br[jq], Br[jq + 2]); hmma0(z[pp][jq] + 2, vr, Bi[jq], Bi[jq + 2]);
                    hmma(z[pp][jq], vi, Bn[jq], Bn[jq + 2]); hmma(z[pp][jq] + 2, vi, Br[jq], Br[jq + 2]);
                }
            }
            u32 pt[2][2];
            if (p == 0) {
                mb_wait(BR + 8 * B_XF, 0);
                mb_wait(BR + 8 * B_TAG, 0);
                tag = lds32(MI + MI_TAG);
#pragma unroll
                for (int pp = 0; pp < 2; pp++)
#pragma unroll
                    for (int im = 0; im < 2; im++) { pt[pp][im] = z[pp][1][2 * im]; z[pp][1][2 * im] = g == 0 ? z[pp][1][2 * im + 1] : z[pp][1][2 * im]; }
            }
#pragma unroll
            for (int pp = 0; pp < 2; pp++)
#pragma unroll
                for (int jq = 0; jq < 2; jq++) stsm4t(za[pp][jq] + p * 16384, z[pp][jq][0], z[pp][jq][1], z[pp][jq][2], z[pp][jq][3]);
            if (p == 0) {
                __syncwarp();
#pragma unroll
                for (int im = 0; im < 2; im++) {
                    sts16p(lane == 0, MI + MI_SIDE + im * 16 + warp * 2, pt[0][im]);
                    pt[0][im] = lane == 0 ? __byte_perm(z[0][0][2 * im], pt[0][im], 0x7610) : pt[0][im];
#pragma unroll
                    for (int pp = 0; pp < 2; pp++)
#pragma unroll
                        for (int e = 0; e < 2; e++) { int n = 2 * t + e; sts16p(g == 0, R0 + pp * 512 + n * 2048 + (2 + im) * 128 + ((warp ^ n) << 4), e ? pt[pp][im] >> 16 : pt[pp][im]); }
                }
            }
            cbar();
            if (p == 0) STAMP(2);
            const u32 base = R0 + p * 16384 + warp * 2048;
            u32 B[4][4];
#pragma unroll
            for (int tl = 0; tl < 4; tl++) ldsm4t(B[tl], base + tl * 512 + (lane >> 3) * 128 + (((lane & 7) ^ warp) << 4));
            __syncwarp();
#pragma unroll
            for (int dir = 0; dir < 2; dir++) {
                u32 cr[2][2], ci[2][2];
#pragma unroll
                for (int kp = 0; kp < 2; kp++) {
                    const u32* b = B[dir * 2 + kp];
                    hmma0(cr[kp], Ab, b[0], b[1]); hmma0(ci[kp], Ab + 8, b[0], b[1]);
                    hmma(cr[kp], Ab + 4, b[2], b[3]); hmma(ci[kp], Ab + 12, b[2], b[3]);
                }
#pragma unroll
                for (int r = 0; r < 2; r++)
                    sts128(base + (g + 8 * r) * 128 + (((dir * 4 + t) ^ ssw(g) ^ fa) << 4), ptag(plo(cr[0][r], ci[0][r]), tag), plo(cr[1][r], ci[1][r]), ptag(phi(cr[0][r], ci[0][r]), tag), phi(cr[1][r], ci[1][r]));
            }
            __syncwarp();
            if (lane == 0) mb_arrive(BR + 8 * (B_ST + p));
        }
        STAMP(28);
        if (warp == 7) {
            u32 b0 = lds32(MI + MI_SIDE + t * 4), b1 = lds32(MI + MI_SIDE + 16 + t * 4);
            float cr[4], ci[4];
            mma0(cr, Ab, b0, b1); mma0(ci, Ab + 8, b0, b1);
            mma(cr, Ab + 4, b0, b1); mma(ci, Ab + 12, b0, b1);
            if (t < 2) st_rlx64(&g_E1x[(g + 8 * t) * 128 + a], t ? pk(cr[2], ci[2]) : pk(cr[0], ci[0]), tag);
        }
    }
    {
        const int k1 = a & 15;
        u32 w[36];
        mb_wait(BR + 8 * B_W, 0);
        {
            u32 cofs[4];
#pragma unroll
            for (int q = 0; q < 4; q++) {
                const int o = 4 * (warp & 3) + (q ^ t);
                cofs[q] = R1 + (g + 32 * t) * 144 + ((warp < 4 ? o : (o == 0 ? 16 : 32 - o)) + (k1 & 7)) * 2;
            }
#pragma unroll
            for (int c = 0; c < 2; c++)
#pragma unroll
                for (int kp = 0; kp < 2; kp++)
#pragma unroll
                    for (int r = 0; r < 2; r++) {
                        u32 v[4];
#pragma unroll
                        for (int q = 0; q < 4; q++) { u32 ad = cofs[q] + c * 18432 + r * 8 * 144 + kp * 64; v[q] = plo(lds16(ad), lds16(ad + 16 * 144)); }
                        const bool s0 = t & 1, s1 = t & 2;
                        u32 x0 = s0 ? v[1] : v[0], x1 = s0 ? v[0] : v[1], x2 = s0 ? v[3] : v[2], x3 = s0 ? v[2] : v[3];
                        v[0] = s1 ? x2 : x0; v[1] = s1 ? x3 : x1; v[2] = s1 ? x0 : x2; v[3] = s1 ? x1 : x3;
#pragma unroll
                        for (int q = 0; q < 4; q++) w[((c * 2 + (q & 1)) * 4 + (q >> 1) * 2 + kp) * 2 + r] = v[q];
                    }
        }
#pragma unroll
        for (int i = 0; i < 4; i++) {
            u32 ad = R1 + (i >> 1) * 18432 + (g + 8 * (i & 1) + 32 * t) * 144 + (64 + (k1 & 7)) * 2;
            w[32 + i] = (a >= 112 && warp == 0) ? (lds16(ad) | (lds16(ad + 16 * 144) << 16)) : 0u;
        }
        __syncwarp();
        if (lane == 0) mb_arrive(BR + 8 * B_FREE);
        STAMP(21);
        w_scale<36>(w, MI, warp, lane, tag);
        STAMP(22);
        mb_wait(BR + 8 * B_T2, 0);
        u32 T[40]; tload<40>(T, TB + 9216, 0, lane);
        if (a >= 112 && warp == 0) {
            u32 d[4][1], o[4][1], wr[1][2] = {{w[32], w[33]}}, wi[1][2] = {{w[34], w[35]}};
#pragma unroll 1
            for (int it = 0;; it++) {
                bool ok = true;
#pragma unroll
                for (int r = 0; r < 4; r++) { uint2 v = ld_rlx64(&g_E1x[k1 * 128 + g + 8 * (t + 4 * r)]); d[r][0] = v.x; ok &= (v.y == tag); }
                if (__all_sync(~0u, ok)) break;
                if (it > SPIN_LIMIT) { TRAP(); break; }
            }
            p2_core<1>(d, o, T, wr, wi);
#pragma unroll
            for (int e = 0; e < 4; e++) st_rlx64(&g_E2x[(2 * t + (e & 1) + 8 * (g + 8 * (e >> 1))) * 16 + k1], o[e][0], tag);
        }
        const int sk = warp ^ ssw(k1);
#pragma unroll 1
        for (int h = 0; h < 2; h++) {
            const u32 base = R0 + h * 16384;
            u32 d[4][4], o[4][4], wr[4][2], wi[4][2];
#pragma unroll
            for (int i = 0; i < 4; i++)
#pragma unroll
                for (int r = 0; r < 2; r++) { wr[i][r] = w[i * 2 + r]; wi[i][r] = w[16 + i * 2 + r]; w[i * 2 + r] = w[8 + i * 2 + r]; w[16 + i * 2 + r] = w[24 + i * 2 + r]; }
            mb_wait(BR + 8 * (B_LD + h), 0);
            if (!h) STAMP(18);
#pragma unroll
            for (int r = 0; r < 4; r++) {
                int aa = g + 8 * (t + 4 * r);
                uint4 v = lds128(base + aa * 128 + ((sk ^ fsw(aa)) << 4));
                d[r][0] = v.x; d[r][1] = v.y; d[r][2] = v.z; d[r][3] = v.w;
            }
            u32 bad0 = 0;
#pragma unroll
            for (int r = 0; r < 4; r++) bad0 |= (d[r][0] ^ tag) | (d[r][2] ^ tag);
            if (__builtin_expect(__any_sync(~0u, bad0 & 1u), 0))
#pragma unroll 1
            for (int it = 0; it < SPIN_LIMIT; it++) {
                u32 bad = 0;
#pragma unroll
                for (int r = 0; r < 4; r++) bad |= (d[r][0] ^ tag) | (d[r][2] ^ tag);
                if (!__any_sync(~0u, bad & 1u)) break;
#pragma unroll
                for (int r = 0; r < 4; r++) {
                    int aa = g + 8 * (t + 4 * r);
                    uint4 v = ld_rlx128(&g_E1[(h * 128 + a) * 1024 + aa * 8 + (sk ^ fsw(aa))]);
                    d[r][0] = v.x; d[r][1] = v.y; d[r][2] = v.z; d[r][3] = v.w;
                }
            }
#pragma unroll
            for (int r = 0; r < 4; r++) { d[r][0] &= ~1u; d[r][2] &= ~1u; }
            p2_core<4>(d, o, T, wr, wi);
            __syncwarp();
#pragma unroll
            for (int e = 0; e < 4; e++) {
                int aa = 2 * t + (e & 1) + 8 * (g + 8 * (e >> 1));
                sts128(base + aa * 128 + ((sk ^ fsw(aa)) << 4), ptag(o[e][0], tag), o[e][1], ptag(o[e][2], tag), o[e][3]);
            }
            __syncwarp();
            if (lane == 0) mb_arrive(BR + 8 * (B_ST + h));
        }
        STAMP(6);
    }
    u32 hn[2][16];
    u32 mykey;
    {
        mb_wait(BR + 8 * B_T3, 0);
        STAMP(20);
        u32 Ab[16]; tload<16>(Ab, TB, 56, lane);
        const u32 emax = lds32(MI + MI_EXP + 128);
        {
            uint4 ev = lds128(MI + MI_EXP + warp * 16);
            const u32 ek[4] = {ev.x, ev.y, ev.z, ev.w};
#pragma unroll
            for (int r = 0; r < 4; r++) {
                float f = __uint_as_float((u32)max(127 + (int)((ek[r] >> (8 * t)) & 255u) - (int)emax, 0) << 23);
                u32 f2 = pk(f, f);
#pragma unroll
                for (int M = 0; M < 2; M++) { Ab[M * 8 + 2 * r] = hmul(Ab[M * 8 + 2 * r], f2); Ab[M * 8 + 2 * r + 1] = hmul(Ab[M * 8 + 2 * r + 1], f2); }
            }
        }
        if (warp == 7) {
            u32 b[4];
#pragma unroll 1
            for (int it = 0;; it++) {
                bool ok = true;
#pragma unroll
                for (int r = 0; r < 4; r++) { uint2 v = ld_rlx64(&g_E2x[a * 16 + t + 4 * r]); b[r] = v.x; ok &= (v.y == tag); }
                if (__all_sync(~0u, ok)) break;
                if (it > SPIN_LIMIT) { TRAP(); break; }
            }
            float c[4];
            mma0(c, Ab, b[0], b[1]); mma(c, Ab + 4, b[2], b[3]); mma(c, Ab + 8, b[0], b[1]); mma(c, Ab + 12, b[2], b[3]);
            u32 v = pk(c[0] * 0.5f, c[2] * 0.5f);
            if (t == 0) { sts16(MI + MI_SIDE + g * 2, v & 0xffffu); sts16(MI + MI_SIDE + 16 + g * 2, v >> 16); }
        }
        u32 T[56]; tload<56>(T, TB, 0, lane);
        __syncwarp();
        if (lane == 0) mb_arrive(BR + 8 * (B_FREE + 1));
        u32 wv[16];
#pragma unroll
        for (int i = 0; i < 16; i++) wv[i] = __ldg((const u32*)grt + (8 * (i >> 2) + g) * 16 + (i & 3) * 4 + t);
        float wsum = 0.f;
#pragma unroll
        for (int i = 0; i < 16; i++) wsum += blo(wv[i]) + bhi(wv[i]);
#pragma unroll
        for (int o = 1; o < 32; o <<= 1) wsum += __shfl_xor_sync(~0u, wsum, o);
        const u32 norm = (emax << 7) | (emax << 23);
        float r0[2][4][4];
#pragma unroll
        for (int p = 0; p < 2; p++) {
            const u32 base = R0 + p * 16384 + warp * 2048;
            mb_wait(BR + 8 * (B_LD + p), 1);
            if (p) STAMP(9); else STAMP(24);
            uint2 B[2][4];
#pragma unroll
            for (int dir = 0; dir < 2; dir++)
#pragma unroll
                for (int r = 0; r < 4; r++) B[dir][r] = lds64(base + (t + 4 * r) * 128 + (((dir * 4 + (g >> 1)) ^ ssw(t) ^ fa) << 4) + (g & 1) * 8);
            u32 bad0 = 0;
#pragma unroll
            for (int r = 0; r < 4; r++) bad0 |= (B[0][r].x ^ tag) | (B[1][r].x ^ tag);
            if (__builtin_expect(__any_sync(~0u, bad0 & 1u), 0))
#pragma unroll 1
            for (int it = 0; it < SPIN_LIMIT; it++) {
                u32 bad = 0;
#pragma unroll
                for (int r = 0; r < 4; r++) bad |= (B[0][r].x ^ tag) | (B[1][r].x ^ tag);
                if (!__any_sync(~0u, bad & 1u)) break;
#pragma unroll
                for (int dir = 0; dir < 2; dir++)
#pragma unroll
                    for (int r = 0; r < 4; r++)
                        B[dir][r] = ld_rlx64((const uint2*)&g_E2[(p * 128 + a) * 1024 + warp * 128 + (t + 4 * r) * 8 + ((dir * 4 + (g >> 1)) ^ ssw(t) ^ fa)] + (g & 1));
            }
#pragma unroll
            for (int r = 0; r < 4; r++) { B[0][r].x &= ~1u; B[1][r].x &= ~1u; }
            __syncwarp();
#pragma unroll
            for (int dir = 0; dir < 2; dir++)
#pragma unroll
                for (int kp = 0; kp < 2; kp++) {
                    u32 cl[2], ch[2];
                    u32 b0 = kp ? B[dir][0].y : B[dir][0].x, b1 = kp ? B[dir][1].y : B[dir][1].x, b2 = kp ? B[dir][2].y : B[dir][2].x, b3 = kp ? B[dir][3].y : B[dir][3].x;
                    hmma0(cl, Ab, b0, b1); hmma0(ch, Ab + 8, b0, b1);
                    hmma(cl, Ab + 4, b2, b3); hmma(ch, Ab + 12, b2, b3);
                    if (p == 0 && dir == 0 && kp == 0) {
                        const bool dc = warp == 0 && t == 0;
                        const u32 fl = dc ? 0x3c003800u : 0x3c003c00u, fh = dc ? 0x00003800u : 0u;
                        cl[0] = hfma(ch[0], fh, hmul(cl[0], fl)); cl[1] = hfma(ch[1], fh, hmul(cl[1], fl));
                    }
                    stsm4(base + (dir * 2 + kp) * 512 + (lane >> 3) * 128 + (((lane & 7) ^ warp) << 4), cl[0], cl[1], ch[0], ch[1]);
                }
            cbar();
            u32 z[2][2][4];
#pragma unroll
            for (int pp = 0; pp < 2; pp++)
#pragma unroll
                for (int jq = 0; jq < 2; jq++) ldsm4t(z[pp][jq], za[pp][jq] + p * 16384);
            if (p == 0) {
#pragma unroll
                for (int im = 0; im < 2; im++)
#pragma unroll
                    for (int pp = 0; pp < 2; pp++) {
                        u32 a0 = R0 + pp * 512 + 2 * t * 2048 + (2 + im) * 128 + ((warp ^ (2 * t)) << 4);
                        u32 a1 = R0 + pp * 512 + (2 * t + 1) * 2048 + (2 + im) * 128 + ((warp ^ (2 * t + 1)) << 4);
                        if (pp == 0) a0 = t == 0 ? MI + MI_SIDE + im * 16 + warp * 2 : a0;
                        const u32 v = plo(lds16(a0), lds16(a1));
                        z[pp][1][2 * im + 1] = g == 0 ? z[pp][1][2 * im] : z[pp][1][2 * im + 1];
                        z[pp][1][2 * im] = g == 0 ? v : z[pp][1][2 * im];
                    }
            }
            u32 vr[4][2], vi[4][2];
#pragma unroll
            for (int rho = 0; rho < 2; rho++) {
                u32 sr[2][2], si[2][2];
#pragma unroll
                for (int pp = 0; pp < 2; pp++) {
                    const u32 *Ar = T + 32 + 12 * pp, *Ai = Ar + 4, *An = Ar + 8;
                    hmma0(sr[pp], Ar, z[pp][0][rho], z[pp][1][rho]); hmma0(si[pp], Ai, z[pp][0][rho], z[pp][1][rho]);
                    hmma(sr[pp], An, z[pp][0][2 + rho], z[pp][1][2 + rho]); hmma(si[pp], Ar, z[pp][0][2 + rho], z[pp][1][2 + rho]);
                }
#pragma unroll
                for (int be = 0; be < 2; be++)
#pragma unroll
                    for (int ga = 0; ga < 2; ga++) {
                        u32 re = be ? hsub(sr[0][ga], sr[1][ga]) : hadd(sr[0][ga], sr[1][ga]);
                        u32 im = be ? hsub(si[0][ga], si[1][ga]) : hadd(si[0][ga], si[1][ga]);
                        int ti = ((p * 2 + rho) * 2 + be) * 2 + ga;
                        cmul(re, im, T[ti], T[16 + ti]);
                        vr[2 * be + ga][rho] = re; vi[2 * be + ga][rho] = im;
                    }
            }
            const u32 *Ar = T + 32 + 12 * p, *Ai = Ar + 4, *An = Ar + 8;
#pragma unroll
            for (int jn = 0; jn < 4; jn++) {
                float r1[2][4];
                float *cr = p ? r1[0] : r0[0][jn], *ci = p ? r1[1] : r0[1][jn];
                mma0(cr, Ar, vr[jn][0], vr[jn][1]); mma0(ci, Ai, vr[jn][0], vr[jn][1]);
                mma(cr, An, vi[jn][0], vi[jn][1]); mma(ci, Ar, vi[jn][0], vi[jn][1]);
                if (p) {
#pragma unroll
                    for (int c = 0; c < 2; c++)
#pragma unroll
                        for (int ga = 0; ga < 2; ga++) {
                            const float *e = r0[c][jn] + 2 * ga, *o = r1[c] + 2 * ga;
                            hh[c][ga * 4 + jn] = bfma(pkb(e[0] + o[0], e[1] + o[1]), norm, hh[c][ga * 4 + jn]);
                            hh[c][(2 + ga) * 4 + jn] = bfma(pkb(e[0] - o[0], e[1] - o[1]), norm, hh[c][(2 + ga) * 4 + jn]);
                        }
                }
            }
        }
        float sm[2], sq[2], mean[2], rstd[2];
#pragma unroll
        for (int c = 0; c < 2; c++) {
            float s0 = 0.f, s1 = 0.f, q0 = 0.f, q1 = 0.f;
#pragma unroll
            for (int i = 0; i < 16; i++) { float lo = blo(hh[c][i]), hi = bhi(hh[c][i]); s0 += lo; s1 += hi; q0 = fmaf(lo, lo, q0); q1 = fmaf(hi, hi, q1); }
            sm[c] = s0 + s1; sq[c] = q0 + q1;
        }
        float c0[4] = {0.f, 0.f, 0.f, 0.f}, c1[4] = {0.f, 0.f, 0.f, 0.f};
#pragma unroll
        for (int i = 0; i < 4; i++) {
            mmab(c0, hh[0][4 * i], hh[1][4 * i], hh[0][4 * i + 1], hh[1][4 * i + 1], wv[4 * i], wv[4 * i + 1]);
            mmab(c1, hh[0][4 * i + 2], hh[1][4 * i + 2], hh[0][4 * i + 3], hh[1][4 * i + 3], wv[4 * i + 2], wv[4 * i + 3]);
        }
        float q0 = (g >> 1) == t ? ((g & 1) ? c0[1] + c1[1] : c0[0] + c1[0]) : 0.f;
        float q1 = (g >> 1) == t ? ((g & 1) ? c0[3] + c1[3] : c0[2] + c1[2]) : 0.f;
        float qq = ((lane & 1) ? q1 : q0) + __shfl_xor_sync(~0u, (lane & 1) ? q0 : q1, 1);
#pragma unroll
        for (int o = 2; o < 32; o <<= 1) qq += __shfl_xor_sync(~0u, qq, o);
        ln_finish(sm, sq, mean, rstd);
        qq = (lane & 1) ? rstd[1] * fmaf(-mean[1], wsum, qq) : rstd[0] * fmaf(-mean[0], wsum, qq);
        u32 kb = pkb(qq, 0.f) & 0xffffu;
        kb = (kb & 0x8000u) ? (~kb & 0xffffu) : (kb | 0x8000u);
        mykey = __reduce_max_sync(~0u, (kb << 16) | (u32)(2047 - (a + 128 * (warp + 8 * (lane & 1)))));
        if (lane == 0) sts32(MI + MI_KEYS + warp * 4, mykey);
        asm volatile("bar.arrive 2, 288;" ::: "memory");
#pragma unroll
        for (int c = 0; c < 2; c++) {
            const float r = rstd[c], mr = -mean[c] * r;
#pragma unroll
            for (int i = 0; i < 16; i++) hn[c][i] = pkb(fmaf(blo(hh[c][i]), r, mr), fmaf(bhi(hh[c][i]), r, mr));
        }
        cbar();
    }
    STAMP(11);
    {
        uint4 k0 = lds128(MI + MI_KEYS), k1 = lds128(MI + MI_KEYS + 16);
        u32 ck = max(max(max(k0.x, k0.y), max(k0.z, k0.w)), max(max(k1.x, k1.y), max(k1.z, k1.w)));
        if (mykey == ck) {
            bool hi = (((2047 - (ck & 0xffffu)) >> 10) & 1) != 0;
#pragma unroll
            for (int q = 0; q < 8; q++) {
                int i = (q >> 1) * 4 + (q & 1) * 2, U = (2 * (8 * (q >> 1) + g) + (q & 1)) * 4 + t;
                st_rlx128(&g_candN[a * 256 + U], hi ? hn[1][i] : hn[0][i], hi ? hn[1][i + 1] : hn[0][i + 1], tag, 0);
            }
#pragma unroll
            for (int q = 0; q < 8; q++) {
                int i = (q >> 1) * 4 + (q & 1) * 2, U = (2 * (8 * (q >> 1) + g) + (q & 1)) * 4 + t;
                st_rlx128(&g_candH[a * 256 + U], hi ? hh[1][i] : hh[0][i], hi ? hh[1][i + 1] : hh[0][i + 1], tag, 0);
            }
        }
    }
#pragma unroll
    for (int c = 0; c < 2; c++)
#pragma unroll
        for (int jn = 0; jn < 4; jn++)
            stsm4(R0 + (warp + 8 * c) * 2048 + xo + (((xh + jn) ^ xs) << 4), badd(hh[c][jn], hn[c][jn]), badd(hh[c][4 + jn], hn[c][4 + jn]),
                  badd(hh[c][8 + jn], hn[c][8 + jn]), badd(hh[c][12 + jn], hn[c][12 + jn]));
    __syncwarp();
    if (lane == 0) mb_arrive(BR + 8 * B_ST);
    u32 G[4][8][4], D[8][2][4];
    if (a < 112) {
        mb_wait(BR + 8 * B_GU, 0);
        const int row = 8 * (lane >> 4) + (lane & 7);
#pragma unroll
        for (int mt = 0; mt < 4; mt++)
#pragma unroll
            for (int s = 0; s < 8; s++)
                ldsm4t(G[mt][s], R2 + (2 * warp + (mt >> 1)) * 8192 + (16 * s + row) * 64 + (((2 * (mt & 1) + ((lane >> 3) & 1)) ^ ((row >> 1) & 3)) << 4));
    }
    STAMP(12);
    u32 gk = 0;
    bool have = false, dld = false;
#pragma unroll 1
    for (int it = 0; it < 64 * SPIN_LIMIT; it++) {
        uint2 rb;
        asm volatile("ld.volatile.shared.v2.u32 {%0, %1}, [%2];" : "=r"(rb.x), "=r"(rb.y) : "r"(MI + MI_RUN) : "memory");
        rb.x = __shfl_sync(~0u, rb.x, 0); rb.y = __shfl_sync(~0u, rb.y, 0);
        if (rb.y == 2 && have && rb.x == gk) {
            mb_wait(BR + 8 * B_TAG, 1);
            rb.x = lds32(MI + MI_GK + 4);
            if (rb.x == gk) break;
            if (lane == 0) sts32(MI + MI_RUN, rb.x);
            __syncwarp();
        }
        if (a < 112 && !dld && __all_sync(~0u, mb_test(BR + 8 * B_WD, 0))) {
            dld = true;
            const int row = 8 * (lane >> 4) + (lane & 7);
#pragma unroll
            for (int mt = 0; mt < 8; mt++)
#pragma unroll
                for (int s = 0; s < 2; s++) ldsm4t(D[mt][s], R1 + (16 * s + row) * 2064 + warp * 256 + mt * 32 + ((lane >> 3) & 1) * 16);
        }
        if (rb.y == 0 || (have && rb.x == gk)) continue;
        gk = rb.x; have = true;
        if (a < 112) {
            uint4 xv;
#pragma unroll 1
            for (int i2 = 0; i2 < SPIN_LIMIT; i2++) {
                xv = ld_rlx128(&g_candN[((2047 - (int)(gk & 0xffffu)) & 127) * 256 + tid]);
                if (__all_sync(~0u, xv.z == tag)) break;
            }
            float acc[4][4];
#pragma unroll
            for (int mt = 0; mt < 4; mt++) { acc[mt][0] = acc[mt][1] = acc[mt][2] = acc[mt][3] = 0.f; }
#pragma unroll
            for (int s = 0; s < 8; s++) {
                u32 b0 = (g == s) ? xv.x : 0u, b1 = (g == s) ? xv.y : 0u;
#pragma unroll
                for (int mt = 0; mt < 4; mt++) mmab(acc[mt], G[mt][s][0], G[mt][s][1], G[mt][s][2], G[mt][s][3], b0, b1);
            }
            float v[8], w4[4], w2[2];
#pragma unroll
            for (int mt = 0; mt < 4; mt++) { v[2 * mt] = acc[mt][0] + acc[mt][1]; v[2 * mt + 1] = acc[mt][2] + acc[mt][3]; }
#pragma unroll
            for (int i = 0; i < 4; i++) w4[i] = ((t & 1) ? v[4 + i] : v[i]) + __shfl_xor_sync(~0u, (t & 1) ? v[i] : v[4 + i], 1);
#pragma unroll
            for (int i = 0; i < 2; i++) w2[i] = ((t & 2) ? w4[2 + i] : w4[i]) + __shfl_xor_sync(~0u, (t & 2) ? w4[i] : w4[2 + i], 2);
            u32 ad = R2 + warp * 16384 + ((t & 1) * 32 + (t >> 1) * 16 + g) * 4;
            sts32(ad, __float_as_uint(w2[0])); sts32(ad + 32, __float_as_uint(w2[1]));
            STAMP(30);
        }
    }
    if (a < 112 && !dld) {
        mb_wait(BR + 8 * B_WD, 0);
        const int row = 8 * (lane >> 4) + (lane & 7);
#pragma unroll
        for (int mt = 0; mt < 8; mt++)
#pragma unroll
            for (int s = 0; s < 2; s++) ldsm4t(D[mt][s], R1 + (16 * s + row) * 2064 + warp * 256 + mt * 32 + ((lane >> 3) & 1) * 16);
    }
    STAMP(19);
    cbar();
    const int wrow = 2047 - (int)(gk & 0xffffu);
    STAMP(31);
    const int wa = wrow & 127;
    if (a < 112) {
        float gv[8], uv[8];
#pragma unroll
        for (int i = 0; i < 8; i++) { gv[i] = __uint_as_float(lds32(R2 + i * 16384 + lane * 4)); uv[i] = __uint_as_float(lds32(R2 + i * 16384 + 128 + lane * 4)); }
        float gs = rbf(((gv[0] + gv[1]) + (gv[2] + gv[3])) + ((gv[4] + gv[5]) + (gv[6] + gv[7])));
        float us = rbf(((uv[0] + uv[1]) + (uv[2] + uv[3])) + ((uv[4] + uv[5]) + (uv[6] + uv[7])));
        float act = rbf(__fdividef(gs, 1.f + __expf(-gs))) * us;
        u32 ap = pkb(act, __shfl_down_sync(~0u, act, 1));
        u32 bb[4];
#pragma unroll
        for (int i = 0; i < 4; i++) bb[i] = __shfl_sync(~0u, ap, 8 * i + 2 * t);
        float y[4][4];
#pragma unroll
        for (int i = 0; i < 4; i++) { y[i][0] = y[i][1] = y[i][2] = y[i][3] = 0.f; }
#pragma unroll
        for (int mt = 0; mt < 8; mt++)
#pragma unroll
            for (int s = 0; s < 2; s++)
                mmab(y[(mt & 1) * 2 + s], D[mt][s][0], D[mt][s][1], D[mt][s][2], D[mt][s][3], (g == mt) ? bb[2 * s] : 0u, (g == mt) ? bb[2 * s + 1] : 0u);
        float o[4];
#pragma unroll
        for (int i = 0; i < 4; i++) o[i] = (y[0][i] + y[1][i]) + (y[2][i] + y[3][i]);
        st_rlx128(&g_part[a * 256 + tid], (__float_as_uint(o[0]) & ~255u) | (tag & 255u), __float_as_uint(o[1]), __float_as_uint(o[2]), __float_as_uint(o[3]));
    }
    STAMP(14);
    float fh = 0.f, fn = 0.f, sg;
    {
        u32 kb = gk >> 16;
        kb = (kb & 0x8000u) ? (kb & 0x7fffu) : (~kb & 0xffffu);
        sg = rbf(__fdividef(1.f, 1.f + __expf(-blo(kb))));
    }
    int col = 0;
    if (warp == 7) {
        int U = 2 * a + ((lane >> 2) & 1), i = lane & 3;
        col = 128 * (U >> 5) + 32 * (U & 3) + ((U & 31) >> 2) + 16 * (i & 1) + 8 * (i >> 1);
        int cu = wa * 256 + (col >> 4) * 4 + ((col >> 1) & 3);
#pragma unroll 1
        for (int it = 0;; it++) {
            uint4 vn = ld_rlx128(&g_candN[cu]), vh = ld_rlx128(&g_candH[cu]);
            u32 n = (col & 8) ? vn.y : vn.x, hv = (col & 8) ? vh.y : vh.x;
            fn = (col & 1) ? bhi(n) : blo(n); fh = (col & 1) ? bhi(hv) : blo(hv);
            if (__all_sync(~0u, vn.z == tag && vh.z == tag)) break;
            if (it > SPIN_LIMIT) { TRAP(); break; }
        }
    } else {
        uint4 pv;
#pragma unroll 1
        for (int it = 0;; it++) {
            pv = ld_rlx128(&g_part[(tid >> 1) * 256 + 2 * a + (tid & 1)]);
            if (__all_sync(~0u, (pv.x & 255u) == (tag & 255u))) break;
            if (it > SPIN_LIMIT) { TRAP(); break; }
        }
        float p0 = __uint_as_float(pv.x & ~255u), p1 = __uint_as_float(pv.y), p2 = __uint_as_float(pv.z), p3 = __uint_as_float(pv.w);
        bool b1 = lane & 2, b2 = lane & 4;
        float s0 = (b1 ? p2 : p0) + __shfl_xor_sync(~0u, b1 ? p0 : p2, 2), s1 = (b1 ? p3 : p1) + __shfl_xor_sync(~0u, b1 ? p1 : p3, 2);
        float s = (b2 ? s1 : s0) + __shfl_xor_sync(~0u, b2 ? s0 : s1, 4);
        s += __shfl_xor_sync(~0u, s, 8); s += __shfl_xor_sync(~0u, s, 16);
        if (lane < 8) sts32(MI + MI_RED2 + (warp * 8 + (lane & 1) * 4 + (lane & 2) + ((lane >> 2) & 1)) * 4, __float_as_uint(s));
    }
    cbar();
    if (warp == 7 && lane < 8) {
        float y = 0.f;
#pragma unroll
        for (int i = 0; i < 7; i++) y += __uint_as_float(lds32(MI + MI_RED2 + (i * 8 + lane) * 4));
        y = rbf(rbf(y) * sg);
        out[(size_t)wrow * 1024 + col] = __float2bfloat16_rn(fh + rbf(fn + y));
    }
    STAMP(15);
    STAMP_END();
}

typedef CUresult (*EncFn)(CUtensorMap*, CUtensorMapDataType, cuuint32_t, void*, const cuuint64_t*, const cuuint64_t*, const cuuint32_t*, const cuuint32_t*,
                          CUtensorMapInterleave, CUtensorMapSwizzle, CUtensorMapL2promotion, CUtensorMapFloatOOBfill);
static void mk2d(EncFn f, CUtensorMap* m, CUtensorMapDataType dt, void* p, uint64_t d0, uint64_t d1, uint64_t pitch, u32 b0, u32 b1, CUtensorMapSwizzle sw, CUtensorMapL2promotion pr) {
    cuuint64_t gd[2] = {d0, d1}, gs[1] = {pitch};
    cuuint32_t bd[2] = {b0, b1}, es[2] = {1, 1};
    CUresult r = f(m, dt, 2, p, gd, gs, bd, es, CU_TENSOR_MAP_INTERLEAVE_NONE, sw, pr, CU_TENSOR_MAP_FLOAT_OOB_FILL_NONE);
    if (r != CUDA_SUCCESS) fprintf(stderr, "tensor map encode failed: %d\n", (int)r);
}

extern "C" void kernel_launch(void* const* d_in, const int* in_sizes, int n_in, void* d_out, int out_size) {
    static EncFn f = nullptr;
    if (!f) {
        void* fn = nullptr;
        cudaDriverEntryPointQueryResult q;
        cudaGetDriverEntryPoint("cuTensorMapEncodeTiled", &fn, cudaEnableDefault, &q);
        f = (EncFn)fn;
        cudaFuncSetAttribute(fused_kernel, cudaFuncAttributeMaxDynamicSharedMemorySize, SMEM_BYTES);
    }
    Maps mp;
    const CUtensorMapDataType BF = CU_TENSOR_MAP_DATA_TYPE_BFLOAT16, U32 = CU_TENSOR_MAP_DATA_TYPE_UINT32;
    const CUtensorMapL2promotion PBOX = PROMO, PN = CU_TENSOR_MAP_L2_PROMOTION_NONE;
    void *e1, *e2;
    cudaGetSymbolAddress(&e1, g_E1);
    cudaGetSymbolAddress(&e2, g_E2);
    mk2d(f, &mp.out, BF, d_out, 64, 32768, 128, 64, 16, CU_TENSOR_MAP_SWIZZLE_128B, PN);
    mk2d(f, &mp.wr, BF, d_in[1], 8208, 128, 16416, 72, 128, CU_TENSOR_MAP_SWIZZLE_NONE, PBOX);
    mk2d(f, &mp.wi, BF, d_in[2], 8208, 128, 16416, 72, 128, CU_TENSOR_MAP_SWIZZLE_NONE, PBOX);
    mk2d(f, &mp.g, BF, d_in[5], 3584, 1024, 7168, 32, 128, CU_TENSOR_MAP_SWIZZLE_64B, PBOX);
    mk2d(f, &mp.u, BF, d_in[6], 3584, 1024, 7168, 32, 128, CU_TENSOR_MAP_SWIZZLE_64B, PBOX);
    mk2d(f, &mp.e1, U32, e1, 4096, 256, 16384, 32, 128, CU_TENSOR_MAP_SWIZZLE_NONE, PN);
    mk2d(f, &mp.e2, U32, e2, 4096, 256, 16384, 32, 128, CU_TENSOR_MAP_SWIZZLE_NONE, PN);
    fused_kernel<<<128, 384, SMEM_BYTES>>>(mp, (const __nv_bfloat16*)d_in[0], (const __nv_bfloat16*)d_in[4], Ptrs{(const char*)d_in[1], (const char*)d_in[2], (const char*)d_in[5], (const char*)d_in[6], (const char*)d_in[7]}, (__nv_bfloat16*)d_out);
}
```
